```python
import torch

def _softmax(x, axis=-1):
    return torch.softmax(x, dim=axis)
def _gelu(x):
    return torch.nn.functional.gelu(x, approximate="tanh")
def _silu(x):
    return torch.nn.functional.silu(x)
def _sigmoid(x):
    return torch.sigmoid(x)
def _layernorm(x, axis=-1, eps=1e-5):
    m = x.mean(dim=axis, keepdim=True)
    v = x.var(dim=axis, keepdim=True, unbiased=False)
    return (x - m) / torch.sqrt(v + eps)
def _scatter_add(tgt, idx, src, axis=0):
    return tgt.clone().index_add_(axis, idx, src)
def _segment_sum(src, seg, n):
    out = torch.zeros((n,) + src.shape[1:], dtype=src.dtype)
    return out.index_add_(0, seg, src)
def _pad(x, pw):
    flat = tuple(v for pair in reversed(pw) for v in pair)
    return torch.nn.functional.pad(x, flat)

kernel_name = 'concat_heads__gqa_block_cached__mha_block_cached__near_ridge'

def setup_inputs():

    _w = (lambda a: (lambda t: t.to(torch.bfloat16) if t.is_floating_point() else t)(torch.as_tensor(a)))
    def _A_setup():
        B, Sq, D = 32, 32, 448
        Hq, Hkv, Sk, Dh = 16, 8, 32, 256
        assert Hq % Hkv == 0, (Hq, Hkv)
        return {
            "x": _w((lambda *s: torch.randn(*s, dtype=torch.bfloat16) * 0.8)(B, Sq, D)),
            "k_cache": _w((lambda *s: torch.randn(*s, dtype=torch.bfloat16) * 0.8)(B, Hkv, Sk, Dh)),
            "v_cache": _w((lambda *s: torch.randn(*s, dtype=torch.bfloat16) * 0.05)(B, Hkv, Sk, Dh)),
            "wq": _w((lambda *s: torch.randn(*s, dtype=torch.bfloat16) * 0.8)(D, Hq * Dh) * (D ** -0.5)),
            "wo": _w((lambda *s: torch.randn(*s, dtype=torch.bfloat16) * 0.05)(Hq * Dh, D) * ((Hq * Dh) ** -0.5)),
        }
    _A_in = _A_setup()

    def _B_setup():
        B, Sq, D = 32, 32, 448
        H, Sk, Dh = 16, 32, 256
        return {
            "x": _w((lambda *s: torch.randn(*s, dtype=torch.bfloat16) * 0.8)(B, Sq, D)),
            "k_cache": _w((lambda *s: torch.randn(*s, dtype=torch.bfloat16) * 0.8)(B, H, Sk, Dh)),
            "v_cache": _w((lambda *s: torch.randn(*s, dtype=torch.bfloat16) * 0.05)(B, H, Sk, Dh)),
            "wq": _w((lambda *s: torch.randn(*s, dtype=torch.bfloat16) * 0.8)(D, H * Dh) * (D ** -0.5)),
            "wo": _w((lambda *s: torch.randn(*s, dtype=torch.bfloat16) * 0.05)(H * Dh, D) * ((H * Dh) ** -0.5)),
        }
    _B_in = _B_setup()

    return {
        "A_x": _A_in["x"],
        "A_k_cache": _A_in["k_cache"],
        "A_v_cache": _A_in["v_cache"],
        "A_wq": _A_in["wq"],
        "A_wo": _A_in["wo"],
        "B_x": _B_in["x"],
        "B_k_cache": _B_in["k_cache"],
        "B_v_cache": _B_in["v_cache"],
        "B_wq": _B_in["wq"],
        "B_wo": _B_in["wo"],
    }

def reference(A_x, A_k_cache, A_v_cache, A_wq, A_wo, B_x, B_k_cache, B_v_cache, B_wq, B_wo):
    def _A_ref(x, k_cache, v_cache, wq, wo):
        B, Sq, D = x.shape
        Hq, Dh = 16, 256
        Hkv = k_cache.shape[1]
        rep = Hq // Hkv
        q = (lambda x, *d: x.permute(*d))((x @ wq).reshape(B, Sq, Hq, Dh), 0, 2, 1, 3)
        k = (lambda x, n, axis: torch.repeat_interleave(x, n, dim=axis))(k_cache, rep, axis=1)
        v = (lambda x, n, axis: torch.repeat_interleave(x, n, dim=axis))(v_cache, rep, axis=1)
        scores = torch.einsum("bhqd,bhkd->bhqk", q, k) * (Dh ** -0.5)
        p = _softmax(scores, axis=-1)
        o = torch.einsum("bhqk,bhkd->bhqd", p, v)
        return (lambda x, *d: x.permute(*d))(o, 0, 2, 1, 3).reshape(B, Sq, Hq * Dh) @ wo

    def _B_ref(x, k_cache, v_cache, wq, wo):
        B, Sq, D = x.shape
        H, Dh = 16, 256
        q = (lambda x, *d: x.permute(*d))((x @ wq).reshape(B, Sq, H, Dh), 0, 2, 1, 3)
        scores = torch.einsum("bhqd,bhkd->bhqk", q, k_cache) * (Dh ** -0.5)
        p = _softmax(scores, axis=-1)
        o = torch.einsum("bhqk,bhkd->bhqd", p, v_cache)
        return (lambda x, *d: x.permute(*d))(o, 0, 2, 1, 3).reshape(B, Sq, H * Dh) @ wo

    a = _A_ref(A_x, A_k_cache, A_v_cache, A_wq, A_wo)
    b = _B_ref(B_x, B_k_cache, B_v_cache, B_wq, B_wo)
    return torch.concatenate([a, b], axis=-1)
```

```cpp
#include <cuda_runtime.h>
#include <cuda_bf16.h>
#include <cuda.h>
#include <stdint.h>

namespace {

constexpr int NSLOT = 14;
constexpr int SLOT_BYTES = 16384;
constexpr int NCHUNK = 7;

__host__ __device__ constexpr int idxX(int i) { return 3 * i; }
__host__ __device__ constexpr int idxWq(int g, int j) { return g == 0 ? 3 * (j / 2) + 1 + (j % 2) : 21 + j; }
__host__ __device__ constexpr int idxK(int h, int w, int half) { return (h == 0 ? 35 : 49) + 2 * half + w; }
__host__ __device__ constexpr int idxV(int h, int w, int half) { return (h == 0 ? 39 : 55) + 2 * half + w; }
__host__ __device__ constexpr int idxWo(int n) { return n < 6 ? 43 + n : (n < 8 ? 47 + n : 51 + n); }
__host__ __device__ constexpr int idxStg(int c) { return 79 + c; }
__host__ __device__ constexpr int pairChunk(int g) {
    return g < 5 ? g : g == 5 ? 0 : g == 6 ? 4 : g == 7 ? 1 : g <= 9 ? 5 : g == 10 ? 2 : g == 11 ? 3 : 6;
}
__host__ __device__ constexpr int pairHead(int g) { return (g < 5 || g == 8 || g == 12) ? 0 : 1; }
constexpr int NREAL = 79;
constexpr int NSTG = 4;
constexpr int NT = NREAL + NSTG;
constexpr int NEARLY = 4;
constexpr int STAG_T0 = 1500;
constexpr int STAG = 200;

enum { T_X = 0, T_WQ, T_K, T_V, T_WO, T_STG };
struct Sched {
    int kind[NT], a[NT], b[NT], c[NT], slot[NT], next[NT];
};
constexpr Sched make_sched() {
    Sched s{};
    for (int i = 0; i < NT; i++) { s.next[i] = -1; s.slot[i] = -1; }
    for (int i = 0; i < 7; i++) { int t = idxX(i); s.kind[t] = T_X; s.a[t] = i; }
    for (int h = 0; h < 2; h++) {
        for (int j = 0; j < 14; j++) { int t = idxWq(h, j); s.kind[t] = T_WQ; s.a[t] = h; s.b[t] = j; }
        for (int w = 0; w < 2; w++)
            for (int f = 0; f < 2; f++) {
                int t = idxK(h, w, f); s.kind[t] = T_K; s.a[t] = h; s.b[t] = w; s.c[t] = f;
                t = idxV(h, w, f); s.kind[t] = T_V; s.a[t] = h; s.b[t] = w; s.c[t] = f;
            }
    }
    for (int n = 0; n < 28; n++) {
        int t = idxWo(n); s.kind[t] = T_WO; s.b[t] = pairChunk(n / 2); s.c[t] = pairHead(n / 2) * 2 + n % 2;
    }
    for (int i = 0; i < NSTG; i++) { int t = idxStg(i); s.kind[t] = T_STG; s.a[t] = i; }
    int rel[NT] = {};
    int n = 0;
    for (int j = 0; j < 14; j++) rel[n++] = idxWq(0, j);
    for (int j = 0; j < 14; j++) { rel[n++] = idxWq(1, j); if (j & 1) rel[n++] = idxX(j / 2); }
    for (int t = 35; t < NREAL; t++) rel[n++] = t;
    int nr = 0;
    for (int k = 0; k < NT; k++) {
        int t = -1;
        if (k >= NSLOT) {
            const int r = rel[k - NSLOT];
            if (r == idxV(0, 0, 0)) t = idxStg(0);
            for (int c = 1; c < NSTG; c++) if (r == idxWo(2 * (c - 1))) t = idxStg(c);
        }
        if (t < 0) t = nr++;
        if (k < NSLOT) s.slot[t] = k;
        else { const int r = rel[k - NSLOT]; s.slot[t] = s.slot[r]; s.next[r] = t; }
    }
    return s;
}
constexpr Sched SCH = make_sched();
template <int I> struct TI {
    static constexpr int kind = SCH.kind[I], a = SCH.a[I], b = SCH.b[I], c = SCH.c[I], slot = SCH.slot[I], next = SCH.next[I];
};

constexpr int BAR_OFF = NSLOT * SLOT_BYTES;
constexpr int FULL_OFF = BAR_OFF;
constexpr int EMPTY_OFF = BAR_OFF + NT * 8;
constexpr int OUTRDY_OFF = BAR_OFF + 2 * NT * 8;
constexpr int SMEM_BYTES = BAR_OFF + 3072;
constexpr uint32_t SMEM_START = 0x400;

struct alignas(64) Maps {
    CUtensorMap x[2], wq[2], k[2], v[2], wo[2], out;
    const uint8_t* px[2];
    const uint8_t* pk[2];
    const uint8_t* pv[2];
    const uint8_t* pwq[2];
    const uint8_t* pwo[2];
    uint32_t zero;
};

__device__ unsigned int g_zero_ctr[16];

template <int MODE>
__device__ __forceinline__ void wgmma_ss_n256_tb1(float (&d)[128], uint64_t descA, uint64_t descB) {
  if constexpr (MODE == 1) {
    asm volatile("wgmma.mma_async.sync.aligned.m64n256k16.f32.bf16.bf16 {%0, %1, %2, %3, %4, %5, %6, %7, %8, %9, %10, %11, %12, %13, %14, %15, %16, %17, %18, %19, %20, %21, %22, %23, %24, %25, %26, %27, %28, %29, %30, %31, %32, %33, %34, %35, %36, %37, %38, %39, %40, %41, %42, %43, %44, %45, %46, %47, %48, %49, %50, %51, %52, %53, %54, %55, %56, %57, %58, %59, %60, %61, %62, %63, %64, %65, %66, %67, %68, %69, %70, %71, %72, %73, %74, %75, %76, %77, %78, %79, %80, %81, %82, %83, %84, %85, %86, %87, %88, %89, %90, %91, %92, %93, %94, %95, %96, %97, %98, %99, %100, %101, %102, %103, %104, %105, %106, %107, %108, %109, %110, %111, %112, %113, %114, %115, %116, %117, %118, %119, %120, %121, %122, %123, %124, %125, %126, %127}, %128, %129, 1, 1, 1, 0, 1;\n"
     : "+f"(d[0]), "+f"(d[1]), "+f"(d[2]), "+f"(d[3]), "+f"(d[4]), "+f"(d[5]), "+f"(d[6]), "+f"(d[7]), "+f"(d[8]), "+f"(d[9]), "+f"(d[10]), "+f"(d[11]), "+f"(d[12]), "+f"(d[13]), "+f"(d[14]), "+f"(d[15]), "+f"(d[16]), "+f"(d[17]), "+f"(d[18]), "+f"(d[19]), "+f"(d[20]), "+f"(d[21]), "+f"(d[22]), "+f"(d[23]), "+f"(d[24]), "+f"(d[25]), "+f"(d[26]), "+f"(d[27]), "+f"(d[28]), "+f"(d[29]), "+f"(d[30]), "+f"(d[31]), "+f"(d[32]), "+f"(d[33]), "+f"(d[34]), "+f"(d[35]), "+f"(d[36]), "+f"(d[37]), "+f"(d[38]), "+f"(d[39]), "+f"(d[40]), "+f"(d[41]), "+f"(d[42]), "+f"(d[43]), "+f"(d[44]), "+f"(d[45]), "+f"(d[46]), "+f"(d[47]), "+f"(d[48]), "+f"(d[49]), "+f"(d[50]), "+f"(d[51]), "+f"(d[52]), "+f"(d[53]), "+f"(d[54]), "+f"(d[55]), "+f"(d[56]), "+f"(d[57]), "+f"(d[58]), "+f"(d[59]), "+f"(d[60]), "+f"(d[61]), "+f"(d[62]), "+f"(d[63]), "+f"(d[64]), "+f"(d[65]), "+f"(d[66]), "+f"(d[67]), "+f"(d[68]), "+f"(d[69]), "+f"(d[70]), "+f"(d[71]), "+f"(d[72]), "+f"(d[73]), "+f"(d[74]), "+f"(d[75]), "+f"(d[76]), "+f"(d[77]), "+f"(d[78]), "+f"(d[79]), "+f"(d[80]), "+f"(d[81]), "+f"(d[82]), "+f"(d[83]), "+f"(d[84]), "+f"(d[85]), "+f"(d[86]), "+f"(d[87]), "+f"(d[88]), "+f"(d[89]), "+f"(d[90]), "+f"(d[91]), "+f"(d[92]), "+f"(d[93]), "+f"(d[94]), "+f"(d[95]), "+f"(d[96]), "+f"(d[97]), "+f"(d[98]), "+f"(d[99]), "+f"(d[100]), "+f"(d[101]), "+f"(d[102]), "+f"(d[103]), "+f"(d[104]), "+f"(d[105]), "+f"(d[106]), "+f"(d[107]), "+f"(d[108]), "+f"(d[109]), "+f"(d[110]), "+f"(d[111]), "+f"(d[112]), "+f"(d[113]), "+f"(d[114]), "+f"(d[115]), "+f"(d[116]), "+f"(d[117]), "+f"(d[118]), "+f"(d[119]), "+f"(d[120]), "+f"(d[121]), "+f"(d[122]), "+f"(d[123]), "+f"(d[124]), "+f"(d[125]), "+f"(d[126]), "+f"(d[127])
     : "l"(descA), "l"(descB));
  } else if constexpr (MODE == 2) {
    asm volatile("wgmma.mma_async.sync.aligned.m64n256k16.f32.bf16.bf16 {%0, %1, %2, %3, %4, %5, %6, %7, %8, %9, %10, %11, %12, %13, %14, %15, %16, %17, %18, %19, %20, %21, %22, %23, %24, %25, %26, %27, %28, %29, %30, %31, %32, %33, %34, %35, %36, %37, %38, %39, %40, %41, %42, %43, %44, %45, %46, %47, %48, %49, %50, %51, %52, %53, %54, %55, %56, %57, %58, %59, %60, %61, %62, %63, %64, %65, %66, %67, %68, %69, %70, %71, %72, %73, %74, %75, %76, %77, %78, %79, %80, %81, %82, %83, %84, %85, %86, %87, %88, %89, %90, %91, %92, %93, %94, %95, %96, %97, %98, %99, %100, %101, %102, %103, %104, %105, %106, %107, %108, %109, %110, %111, %112, %113, %114, %115, %116, %117, %118, %119, %120, %121, %122, %123, %124, %125, %126, %127}, %128, %129, 0, 1, 1, 0, 1;\n"
     : "+f"(d[0]), "+f"(d[1]), "+f"(d[2]), "+f"(d[3]), "+f"(d[4]), "+f"(d[5]), "+f"(d[6]), "+f"(d[7]), "+f"(d[8]), "+f"(d[9]), "+f"(d[10]), "+f"(d[11]), "+f"(d[12]), "+f"(d[13]), "+f"(d[14]), "+f"(d[15]), "+f"(d[16]), "+f"(d[17]), "+f"(d[18]), "+f"(d[19]), "+f"(d[20]), "+f"(d[21]), "+f"(d[22]), "+f"(d[23]), "+f"(d[24]), "+f"(d[25]), "+f"(d[26]), "+f"(d[27]), "+f"(d[28]), "+f"(d[29]), "+f"(d[30]), "+f"(d[31]), "+f"(d[32]), "+f"(d[33]), "+f"(d[34]), "+f"(d[35]), "+f"(d[36]), "+f"(d[37]), "+f"(d[38]), "+f"(d[39]), "+f"(d[40]), "+f"(d[41]), "+f"(d[42]), "+f"(d[43]), "+f"(d[44]), "+f"(d[45]), "+f"(d[46]), "+f"(d[47]), "+f"(d[48]), "+f"(d[49]), "+f"(d[50]), "+f"(d[51]), "+f"(d[52]), "+f"(d[53]), "+f"(d[54]), "+f"(d[55]), "+f"(d[56]), "+f"(d[57]), "+f"(d[58]), "+f"(d[59]), "+f"(d[60]), "+f"(d[61]), "+f"(d[62]), "+f"(d[63]), "+f"(d[64]), "+f"(d[65]), "+f"(d[66]), "+f"(d[67]), "+f"(d[68]), "+f"(d[69]), "+f"(d[70]), "+f"(d[71]), "+f"(d[72]), "+f"(d[73]), "+f"(d[74]), "+f"(d[75]), "+f"(d[76]), "+f"(d[77]), "+f"(d[78]), "+f"(d[79]), "+f"(d[80]), "+f"(d[81]), "+f"(d[82]), "+f"(d[83]), "+f"(d[84]), "+f"(d[85]), "+f"(d[86]), "+f"(d[87]), "+f"(d[88]), "+f"(d[89]), "+f"(d[90]), "+f"(d[91]), "+f"(d[92]), "+f"(d[93]), "+f"(d[94]), "+f"(d[95]), "+f"(d[96]), "+f"(d[97]), "+f"(d[98]), "+f"(d[99]), "+f"(d[100]), "+f"(d[101]), "+f"(d[102]), "+f"(d[103]), "+f"(d[104]), "+f"(d[105]), "+f"(d[106]), "+f"(d[107]), "+f"(d[108]), "+f"(d[109]), "+f"(d[110]), "+f"(d[111]), "+f"(d[112]), "+f"(d[113]), "+f"(d[114]), "+f"(d[115]), "+f"(d[116]), "+f"(d[117]), "+f"(d[118]), "+f"(d[119]), "+f"(d[120]), "+f"(d[121]), "+f"(d[122]), "+f"(d[123]), "+f"(d[124]), "+f"(d[125]), "+f"(d[126]), "+f"(d[127])
     : "l"(descA), "l"(descB));
  } else {
    asm volatile("wgmma.mma_async.sync.aligned.m64n256k16.f32.bf16.bf16 {%0, %1, %2, %3, %4, %5, %6, %7, %8, %9, %10, %11, %12, %13, %14, %15, %16, %17, %18, %19, %20, %21, %22, %23, %24, %25, %26, %27, %28, %29, %30, %31, %32, %33, %34, %35, %36, %37, %38, %39, %40, %41, %42, %43, %44, %45, %46, %47, %48, %49, %50, %51, %52, %53, %54, %55, %56, %57, %58, %59, %60, %61, %62, %63, %64, %65, %66, %67, %68, %69, %70, %71, %72, %73, %74, %75, %76, %77, %78, %79, %80, %81, %82, %83, %84, %85, %86, %87, %88, %89, %90, %91, %92, %93, %94, %95, %96, %97, %98, %99, %100, %101, %102, %103, %104, %105, %106, %107, %108, %109, %110, %111, %112, %113, %114, %115, %116, %117, %118, %119, %120, %121, %122, %123, %124, %125, %126, %127}, %128, %129, 0, 1, 1, 0, 1;\n"
     : "=f"(d[0]), "=f"(d[1]), "=f"(d[2]), "=f"(d[3]), "=f"(d[4]), "=f"(d[5]), "=f"(d[6]), "=f"(d[7]), "=f"(d[8]), "=f"(d[9]), "=f"(d[10]), "=f"(d[11]), "=f"(d[12]), "=f"(d[13]), "=f"(d[14]), "=f"(d[15]), "=f"(d[16]), "=f"(d[17]), "=f"(d[18]), "=f"(d[19]), "=f"(d[20]), "=f"(d[21]), "=f"(d[22]), "=f"(d[23]), "=f"(d[24]), "=f"(d[25]), "=f"(d[26]), "=f"(d[27]), "=f"(d[28]), "=f"(d[29]), "=f"(d[30]), "=f"(d[31]), "=f"(d[32]), "=f"(d[33]), "=f"(d[34]), "=f"(d[35]), "=f"(d[36]), "=f"(d[37]), "=f"(d[38]), "=f"(d[39]), "=f"(d[40]), "=f"(d[41]), "=f"(d[42]), "=f"(d[43]), "=f"(d[44]), "=f"(d[45]), "=f"(d[46]), "=f"(d[47]), "=f"(d[48]), "=f"(d[49]), "=f"(d[50]), "=f"(d[51]), "=f"(d[52]), "=f"(d[53]), "=f"(d[54]), "=f"(d[55]), "=f"(d[56]), "=f"(d[57]), "=f"(d[58]), "=f"(d[59]), "=f"(d[60]), "=f"(d[61]), "=f"(d[62]), "=f"(d[63]), "=f"(d[64]), "=f"(d[65]), "=f"(d[66]), "=f"(d[67]), "=f"(d[68]), "=f"(d[69]), "=f"(d[70]), "=f"(d[71]), "=f"(d[72]), "=f"(d[73]), "=f"(d[74]), "=f"(d[75]), "=f"(d[76]), "=f"(d[77]), "=f"(d[78]), "=f"(d[79]), "=f"(d[80]), "=f"(d[81]), "=f"(d[82]), "=f"(d[83]), "=f"(d[84]), "=f"(d[85]), "=f"(d[86]), "=f"(d[87]), "=f"(d[88]), "=f"(d[89]), "=f"(d[90]), "=f"(d[91]), "=f"(d[92]), "=f"(d[93]), "=f"(d[94]), "=f"(d[95]), "=f"(d[96]), "=f"(d[97]), "=f"(d[98]), "=f"(d[99]), "=f"(d[100]), "=f"(d[101]), "=f"(d[102]), "=f"(d[103]), "=f"(d[104]), "=f"(d[105]), "=f"(d[106]), "=f"(d[107]), "=f"(d[108]), "=f"(d[109]), "=f"(d[110]), "=f"(d[111]), "=f"(d[112]), "=f"(d[113]), "=f"(d[114]), "=f"(d[115]), "=f"(d[116]), "=f"(d[117]), "=f"(d[118]), "=f"(d[119]), "=f"(d[120]), "=f"(d[121]), "=f"(d[122]), "=f"(d[123]), "=f"(d[124]), "=f"(d[125]), "=f"(d[126]), "=f"(d[127])
     : "l"(descA), "l"(descB));
  }
}
template <int MODE>
__device__ __forceinline__ void wgmma_rs_n64_tb0(float (&d)[32], uint32_t a0, uint32_t a1, uint32_t a2, uint32_t a3, uint64_t descB) {
  if constexpr (MODE == 1) {
    asm volatile("wgmma.mma_async.sync.aligned.m64n64k16.f32.bf16.bf16 {%0, %1, %2, %3, %4, %5, %6, %7, %8, %9, %10, %11, %12, %13, %14, %15, %16, %17, %18, %19, %20, %21, %22, %23, %24, %25, %26, %27, %28, %29, %30, %31}, {%32, %33, %34, %35}, %36, 1, 1, 1, 0;\n"
     : "+f"(d[0]), "+f"(d[1]), "+f"(d[2]), "+f"(d[3]), "+f"(d[4]), "+f"(d[5]), "+f"(d[6]), "+f"(d[7]), "+f"(d[8]), "+f"(d[9]), "+f"(d[10]), "+f"(d[11]), "+f"(d[12]), "+f"(d[13]), "+f"(d[14]), "+f"(d[15]), "+f"(d[16]), "+f"(d[17]), "+f"(d[18]), "+f"(d[19]), "+f"(d[20]), "+f"(d[21]), "+f"(d[22]), "+f"(d[23]), "+f"(d[24]), "+f"(d[25]), "+f"(d[26]), "+f"(d[27]), "+f"(d[28]), "+f"(d[29]), "+f"(d[30]), "+f"(d[31])
     : "r"(a0), "r"(a1), "r"(a2), "r"(a3), "l"(descB));
  } else if constexpr (MODE == 2) {
    asm volatile("wgmma.mma_async.sync.aligned.m64n64k16.f32.bf16.bf16 {%0, %1, %2, %3, %4, %5, %6, %7, %8, %9, %10, %11, %12, %13, %14, %15, %16, %17, %18, %19, %20, %21, %22, %23, %24, %25, %26, %27, %28, %29, %30, %31}, {%32, %33, %34, %35}, %36, 0, 1, 1, 0;\n"
     : "+f"(d[0]), "+f"(d[1]), "+f"(d[2]), "+f"(d[3]), "+f"(d[4]), "+f"(d[5]), "+f"(d[6]), "+f"(d[7]), "+f"(d[8]), "+f"(d[9]), "+f"(d[10]), "+f"(d[11]), "+f"(d[12]), "+f"(d[13]), "+f"(d[14]), "+f"(d[15]), "+f"(d[16]), "+f"(d[17]), "+f"(d[18]), "+f"(d[19]), "+f"(d[20]), "+f"(d[21]), "+f"(d[22]), "+f"(d[23]), "+f"(d[24]), "+f"(d[25]), "+f"(d[26]), "+f"(d[27]), "+f"(d[28]), "+f"(d[29]), "+f"(d[30]), "+f"(d[31])
     : "r"(a0), "r"(a1), "r"(a2), "r"(a3), "l"(descB));
  } else {
    asm volatile("wgmma.mma_async.sync.aligned.m64n64k16.f32.bf16.bf16 {%0, %1, %2, %3, %4, %5, %6, %7, %8, %9, %10, %11, %12, %13, %14, %15, %16, %17, %18, %19, %20, %21, %22, %23, %24, %25, %26, %27, %28, %29, %30, %31}, {%32, %33, %34, %35}, %36, 0, 1, 1, 0;\n"
     : "=f"(d[0]), "=f"(d[1]), "=f"(d[2]), "=f"(d[3]), "=f"(d[4]), "=f"(d[5]), "=f"(d[6]), "=f"(d[7]), "=f"(d[8]), "=f"(d[9]), "=f"(d[10]), "=f"(d[11]), "=f"(d[12]), "=f"(d[13]), "=f"(d[14]), "=f"(d[15]), "=f"(d[16]), "=f"(d[17]), "=f"(d[18]), "=f"(d[19]), "=f"(d[20]), "=f"(d[21]), "=f"(d[22]), "=f"(d[23]), "=f"(d[24]), "=f"(d[25]), "=f"(d[26]), "=f"(d[27]), "=f"(d[28]), "=f"(d[29]), "=f"(d[30]), "=f"(d[31])
     : "r"(a0), "r"(a1), "r"(a2), "r"(a3), "l"(descB));
  }
}
template <int MODE>
__device__ __forceinline__ void wgmma_rs_n64_tb1(float (&d)[32], uint32_t a0, uint32_t a1, uint32_t a2, uint32_t a3, uint64_t descB) {
  if constexpr (MODE == 1) {
    asm volatile("wgmma.mma_async.sync.aligned.m64n64k16.f32.bf16.bf16 {%0, %1, %2, %3, %4, %5, %6, %7, %8, %9, %10, %11, %12, %13, %14, %15, %16, %17, %18, %19, %20, %21, %22, %23, %24, %25, %26, %27, %28, %29, %30, %31}, {%32, %33, %34, %35}, %36, 1, 1, 1, 1;\n"
     : "+f"(d[0]), "+f"(d[1]), "+f"(d[2]), "+f"(d[3]), "+f"(d[4]), "+f"(d[5]), "+f"(d[6]), "+f"(d[7]), "+f"(d[8]), "+f"(d[9]), "+f"(d[10]), "+f"(d[11]), "+f"(d[12]), "+f"(d[13]), "+f"(d[14]), "+f"(d[15]), "+f"(d[16]), "+f"(d[17]), "+f"(d[18]), "+f"(d[19]), "+f"(d[20]), "+f"(d[21]), "+f"(d[22]), "+f"(d[23]), "+f"(d[24]), "+f"(d[25]), "+f"(d[26]), "+f"(d[27]), "+f"(d[28]), "+f"(d[29]), "+f"(d[30]), "+f"(d[31])
     : "r"(a0), "r"(a1), "r"(a2), "r"(a3), "l"(descB));
  } else if constexpr (MODE == 2) {
    asm volatile("wgmma.mma_async.sync.aligned.m64n64k16.f32.bf16.bf16 {%0, %1, %2, %3, %4, %5, %6, %7, %8, %9, %10, %11, %12, %13, %14, %15, %16, %17, %18, %19, %20, %21, %22, %23, %24, %25, %26, %27, %28, %29, %30, %31}, {%32, %33, %34, %35}, %36, 0, 1, 1, 1;\n"
     : "+f"(d[0]), "+f"(d[1]), "+f"(d[2]), "+f"(d[3]), "+f"(d[4]), "+f"(d[5]), "+f"(d[6]), "+f"(d[7]), "+f"(d[8]), "+f"(d[9]), "+f"(d[10]), "+f"(d[11]), "+f"(d[12]), "+f"(d[13]), "+f"(d[14]), "+f"(d[15]), "+f"(d[16]), "+f"(d[17]), "+f"(d[18]), "+f"(d[19]), "+f"(d[20]), "+f"(d[21]), "+f"(d[22]), "+f"(d[23]), "+f"(d[24]), "+f"(d[25]), "+f"(d[26]), "+f"(d[27]), "+f"(d[28]), "+f"(d[29]), "+f"(d[30]), "+f"(d[31])
     : "r"(a0), "r"(a1), "r"(a2), "r"(a3), "l"(descB));
  } else {
    asm volatile("wgmma.mma_async.sync.aligned.m64n64k16.f32.bf16.bf16 {%0, %1, %2, %3, %4, %5, %6, %7, %8, %9, %10, %11, %12, %13, %14, %15, %16, %17, %18, %19, %20, %21, %22, %23, %24, %25, %26, %27, %28, %29, %30, %31}, {%32, %33, %34, %35}, %36, 0, 1, 1, 1;\n"
     : "=f"(d[0]), "=f"(d[1]), "=f"(d[2]), "=f"(d[3]), "=f"(d[4]), "=f"(d[5]), "=f"(d[6]), "=f"(d[7]), "=f"(d[8]), "=f"(d[9]), "=f"(d[10]), "=f"(d[11]), "=f"(d[12]), "=f"(d[13]), "=f"(d[14]), "=f"(d[15]), "=f"(d[16]), "=f"(d[17]), "=f"(d[18]), "=f"(d[19]), "=f"(d[20]), "=f"(d[21]), "=f"(d[22]), "=f"(d[23]), "=f"(d[24]), "=f"(d[25]), "=f"(d[26]), "=f"(d[27]), "=f"(d[28]), "=f"(d[29]), "=f"(d[30]), "=f"(d[31])
     : "r"(a0), "r"(a1), "r"(a2), "r"(a3), "l"(descB));
  }
}
template <int MODE>
__device__ __forceinline__ void wgmma_sp_rs_n64_tb1(float (&d)[32], uint32_t a0, uint32_t a1, uint32_t a2, uint32_t a3, uint64_t descB, uint32_t meta) {
  if constexpr (MODE == 1) {
    asm volatile("wgmma.mma_async.sp.sync.aligned.m64n64k32.f32.bf16.bf16 {%0, %1, %2, %3, %4, %5, %6, %7, %8, %9, %10, %11, %12, %13, %14, %15, %16, %17, %18, %19, %20, %21, %22, %23, %24, %25, %26, %27, %28, %29, %30, %31}, {%32, %33, %34, %35}, %36, %37, 0, 1, 1, 1, 1;\n"
     : "+f"(d[0]), "+f"(d[1]), "+f"(d[2]), "+f"(d[3]), "+f"(d[4]), "+f"(d[5]), "+f"(d[6]), "+f"(d[7]), "+f"(d[8]), "+f"(d[9]), "+f"(d[10]), "+f"(d[11]), "+f"(d[12]), "+f"(d[13]), "+f"(d[14]), "+f"(d[15]), "+f"(d[16]), "+f"(d[17]), "+f"(d[18]), "+f"(d[19]), "+f"(d[20]), "+f"(d[21]), "+f"(d[22]), "+f"(d[23]), "+f"(d[24]), "+f"(d[25]), "+f"(d[26]), "+f"(d[27]), "+f"(d[28]), "+f"(d[29]), "+f"(d[30]), "+f"(d[31])
     : "r"(a0), "r"(a1), "r"(a2), "r"(a3), "l"(descB), "r"(meta));
  } else if constexpr (MODE == 2) {
    asm volatile("wgmma.mma_async.sp.sync.aligned.m64n64k32.f32.bf16.bf16 {%0, %1, %2, %3, %4, %5, %6, %7, %8, %9, %10, %11, %12, %13, %14, %15, %16, %17, %18, %19, %20, %21, %22, %23, %24, %25, %26, %27, %28, %29, %30, %31}, {%32, %33, %34, %35}, %36, %37, 0, 0, 1, 1, 1;\n"
     : "+f"(d[0]), "+f"(d[1]), "+f"(d[2]), "+f"(d[3]), "+f"(d[4]), "+f"(d[5]), "+f"(d[6]), "+f"(d[7]), "+f"(d[8]), "+f"(d[9]), "+f"(d[10]), "+f"(d[11]), "+f"(d[12]), "+f"(d[13]), "+f"(d[14]), "+f"(d[15]), "+f"(d[16]), "+f"(d[17]), "+f"(d[18]), "+f"(d[19]), "+f"(d[20]), "+f"(d[21]), "+f"(d[22]), "+f"(d[23]), "+f"(d[24]), "+f"(d[25]), "+f"(d[26]), "+f"(d[27]), "+f"(d[28]), "+f"(d[29]), "+f"(d[30]), "+f"(d[31])
     : "r"(a0), "r"(a1), "r"(a2), "r"(a3), "l"(descB), "r"(meta));
  } else {
    asm volatile("wgmma.mma_async.sp.sync.aligned.m64n64k32.f32.bf16.bf16 {%0, %1, %2, %3, %4, %5, %6, %7, %8, %9, %10, %11, %12, %13, %14, %15, %16, %17, %18, %19, %20, %21, %22, %23, %24, %25, %26, %27, %28, %29, %30, %31}, {%32, %33, %34, %35}, %36, %37, 0, 0, 1, 1, 1;\n"
     : "=f"(d[0]), "=f"(d[1]), "=f"(d[2]), "=f"(d[3]), "=f"(d[4]), "=f"(d[5]), "=f"(d[6]), "=f"(d[7]), "=f"(d[8]), "=f"(d[9]), "=f"(d[10]), "=f"(d[11]), "=f"(d[12]), "=f"(d[13]), "=f"(d[14]), "=f"(d[15]), "=f"(d[16]), "=f"(d[17]), "=f"(d[18]), "=f"(d[19]), "=f"(d[20]), "=f"(d[21]), "=f"(d[22]), "=f"(d[23]), "=f"(d[24]), "=f"(d[25]), "=f"(d[26]), "=f"(d[27]), "=f"(d[28]), "=f"(d[29]), "=f"(d[30]), "=f"(d[31])
     : "r"(a0), "r"(a1), "r"(a2), "r"(a3), "l"(descB), "r"(meta));
  }
}


__device__ __forceinline__ void wgmma_fence() { asm volatile("wgmma.fence.sync.aligned;" ::: "memory"); }
__device__ __forceinline__ void wgmma_commit() { asm volatile("wgmma.commit_group.sync.aligned;" ::: "memory"); }
template <int N>
__device__ __forceinline__ void wgmma_wait() { asm volatile("wgmma.wait_group.sync.aligned %0;" ::"n"(N) : "memory"); }

template <int N>
__device__ __forceinline__ void fence_regs(float (&d)[N]) {
#pragma unroll
    for (int i = 0; i < N; i++) asm volatile("" : "+f"(d[i])::"memory");
}

__device__ __forceinline__ bool elect_one() {
    uint32_t r;
    asm volatile("{\n.reg .pred p;\nelect.sync _|p, 0xffffffff;\nselp.u32 %0, 1, 0, p;\n}\n" : "=r"(r));
    return r != 0;
}
__device__ __forceinline__ void mbar_init(uint32_t bar, uint32_t count) {
    asm volatile("mbarrier.init.shared::cta.b64 [%0], %1;" ::"r"(bar), "r"(count) : "memory");
}
__device__ __forceinline__ bool mbar_try(uint32_t bar) {
    uint32_t ok;
    asm volatile(
        "{\n.reg .pred p;\nmbarrier.try_wait.parity.shared::cta.b64 p, [%1], 0;\nselp.u32 %0, 1, 0, p;\n}\n"
        : "=r"(ok) : "r"(bar) : "memory");
    return ok != 0;
}
constexpr int WAIT_BUDGET = 1 << 20;
__device__ __forceinline__ void mbar_wait(uint32_t bar, int& budget) {
    while (!mbar_try(bar)) { if (--budget < 0) break; }
}
__device__ __forceinline__ void mbar_expect_tx(uint32_t bar, uint32_t bytes) {
    asm volatile("mbarrier.arrive.expect_tx.shared::cta.b64 _, [%0], %1;" ::"r"(bar), "r"(bytes) : "memory");
}
__device__ __forceinline__ void mbar_arrive(uint32_t bar, uint32_t count) {
    asm volatile("mbarrier.arrive.shared::cta.b64 _, [%0], %1;" ::"r"(bar), "r"(count) : "memory");
}
__device__ __forceinline__ void tma_2d(uint32_t dst, const CUtensorMap* m, uint32_t bar, int c0, int c1) {
    asm volatile("cp.async.bulk.tensor.2d.shared::cluster.global.mbarrier::complete_tx::bytes [%0], [%1, {%3, %4}], [%2];"
                 ::"r"(dst), "l"(m), "r"(bar), "r"(c0), "r"(c1) : "memory");
}
__device__ __forceinline__ void tma_3d(uint32_t dst, const CUtensorMap* m, uint32_t bar, int c0, int c1, int c2) {
    asm volatile("cp.async.bulk.tensor.3d.shared::cluster.global.mbarrier::complete_tx::bytes [%0], [%1, {%3, %4, %5}], [%2];"
                 ::"r"(dst), "l"(m), "r"(bar), "r"(c0), "r"(c1), "r"(c2) : "memory");
}
__device__ __forceinline__ void tma_4d(uint32_t dst, const CUtensorMap* m, uint32_t bar, int c0, int c1, int c2, int c3) {
    asm volatile("cp.async.bulk.tensor.4d.shared::cluster.global.mbarrier::complete_tx::bytes [%0], [%1, {%3, %4, %5, %6}], [%2];"
                 ::"r"(dst), "l"(m), "r"(bar), "r"(c0), "r"(c1), "r"(c2), "r"(c3) : "memory");
}
__device__ __forceinline__ void tma_5d(uint32_t dst, const CUtensorMap* m, uint32_t bar, int c0, int c1, int c2, int c3, int c4) {
    asm volatile("cp.async.bulk.tensor.5d.shared::cluster.global.mbarrier::complete_tx::bytes [%0], [%1, {%3, %4, %5, %6, %7}], [%2];"
                 ::"r"(dst), "l"(m), "r"(bar), "r"(c0), "r"(c1), "r"(c2), "r"(c3), "r"(c4) : "memory");
}
__device__ __forceinline__ void tma_red_2d(const CUtensorMap* m, uint32_t src, int c0, int c1) {
    asm volatile("cp.reduce.async.bulk.tensor.2d.global.shared::cta.add.tile.bulk_group [%0, {%2, %3}], [%1];"
                 ::"l"(m), "r"(src), "r"(c0), "r"(c1) : "memory");
}
__device__ __forceinline__ void prefetch_map(const CUtensorMap* m) {
    asm volatile("prefetch.tensormap [%0];" ::"l"(m) : "memory");
}
__device__ __forceinline__ uint32_t pack_bf16(float lo, float hi) {
    uint32_t r;
    asm("cvt.rn.bf16x2.f32 %0, %1, %2;" : "=r"(r) : "f"(hi), "f"(lo));
    return r;
}
__device__ __forceinline__ uint32_t pack_bf16_v(float lo, float hi) {
    uint32_t r;
    asm volatile("cvt.rn.bf16x2.f32 %0, %1, %2;" : "=r"(r) : "f"(hi), "f"(lo));
    return r;
}
__device__ __forceinline__ void stmatrix_x4(uint32_t addr, uint32_t r0, uint32_t r1, uint32_t r2, uint32_t r3) {
    asm volatile("stmatrix.sync.aligned.m8n8.x4.shared.b16 [%0], {%1, %2, %3, %4};" ::"r"(addr), "r"(r0), "r"(r1), "r"(r2), "r"(r3) : "memory");
}
__device__ __forceinline__ float ex2(float x) {
    float y;
    asm("ex2.approx.ftz.f32 %0, %1;" : "=f"(y) : "f"(x));
    return y;
}
__device__ __forceinline__ uint64_t mk_desc(uint32_t base16, uint32_t off_bytes, uint32_t lbo_bytes) {
    uint32_t lo = base16 + (off_bytes >> 4) + ((lbo_bytes >> 4) << 16);
    uint32_t hi = (1024u >> 4) | (1u << 30);
    return ((uint64_t)hi << 32) | lo;
}

struct Ctx {
    uint32_t sbase;
    static constexpr uint32_t base16 = SMEM_START >> 4;
    int lane, wg, warp;
    int budget;
};

template <int I>
__device__ __forceinline__ void wait_full(Ctx& c) { mbar_wait(c.sbase + FULL_OFF + I * 8, c.budget); }
template <int I>
__device__ __forceinline__ void release(Ctx& c) {
    if constexpr (TI<I>::next >= 0) {
        if (c.lane == 0) mbar_arrive(c.sbase + EMPTY_OFF + TI<I>::next * 8, 1u);
    }
}
template <int I>
__device__ __forceinline__ void wait_full_w(Ctx& c) { mbar_wait(c.sbase + FULL_OFF + (I + c.wg) * 8, c.budget); }
template <int I>
__device__ __forceinline__ void release_w(Ctx& c) {
    constexpr int n0 = TI<I>::next, n1 = TI<I + 1>::next;
    static_assert(n0 >= 0 && n1 >= 0, "");
    if (c.lane == 0) mbar_arrive(c.sbase + EMPTY_OFF + (c.wg ? n1 : n0) * 8, 2u);
}
template <int I>
__device__ __forceinline__ uint32_t slot_off_w(Ctx& c) { return (c.wg ? TI<I + 1>::slot : TI<I>::slot) * SLOT_BYTES; }

template <int G, int J>
__device__ __forceinline__ void g1_step(Ctx& c, float (&acc)[128]) {
    if constexpr (G == 0 && (J % 2) == 0) wait_full<idxX(J / 2)>(c);
    wait_full<idxWq(G, J)>(c);
    wgmma_fence();
    constexpr uint32_t xo = TI<idxX(J / 2)>::slot * SLOT_BYTES + (J % 2) * 64;
    constexpr uint32_t wo = TI<idxWq(G, J)>::slot * SLOT_BYTES;
    const uint32_t a16 = c.base16 + c.wg * 512;
    wgmma_ss_n256_tb1<(J != 0)>(acc, mk_desc(a16, xo, 16), mk_desc(c.base16, wo, 4096));
    wgmma_ss_n256_tb1<1>(acc, mk_desc(a16, xo + 32, 16), mk_desc(c.base16, wo + 2048, 4096));
    wgmma_commit();
}
template <int G, int J>
__device__ __forceinline__ void g1_release(Ctx& c) {
    release<idxWq(G, J)>(c);
    if constexpr (G == 1 && (J % 2) == 1) release<idxX(J / 2)>(c);
}
template <int G, int J>
__device__ __forceinline__ void g1_range(Ctx& c, float (&acc)[128]) {
    if constexpr (J < 14) {
        g1_step<G, J>(c, acc);
        if constexpr (J > 0) { wgmma_wait<1>(); g1_release<G, J - 1>(c); }
        g1_range<G, J + 1>(c, acc);
    } else {
        wgmma_wait<0>();
        fence_regs(acc);
        g1_release<G, 13>(c);
    }
}

template <int H>
__device__ __forceinline__ void s_issue(Ctx& c, float (&s)[32], const uint32_t (&q)[64]) {
    wait_full_w<idxK(H, 0, 0)>(c);
    wait_full_w<idxK(H, 0, 1)>(c);
    const uint32_t k0 = c.base16 + (slot_off_w<idxK(H, 0, 0)>(c) >> 4);
    const uint32_t k1 = c.base16 + (slot_off_w<idxK(H, 0, 1)>(c) >> 4);
    wgmma_fence();
#pragma unroll
    for (int kk = 0; kk < 16; kk++) {
        uint64_t d = mk_desc(kk < 8 ? k0 : k1, ((kk / 4) % 2) * 8192 + (kk % 4) * 32, 16);
        if (kk == 0) wgmma_rs_n64_tb0<(H == 0 ? 0 : 2)>(s, q[0], q[1], q[2], q[3], d);
        else wgmma_rs_n64_tb0<1>(s, q[4 * kk], q[4 * kk + 1], q[4 * kk + 2], q[4 * kk + 3], d);
    }
    wgmma_commit();
}

__device__ __forceinline__ void softmax(Ctx& c, const float (&s)[32], uint32_t (&pa)[8]) {
    const bool hi = c.warp >= 2;
    float v[16];
#pragma unroll
    for (int i = 0; i < 16; i++) v[i] = hi ? s[16 + i] : s[i];
    float m0 = fmaxf(fmaxf(fmaxf(v[0], v[1]), fmaxf(v[4], v[5])), fmaxf(fmaxf(v[8], v[9]), fmaxf(v[12], v[13])));
    float m1 = fmaxf(fmaxf(fmaxf(v[2], v[3]), fmaxf(v[6], v[7])), fmaxf(fmaxf(v[10], v[11]), fmaxf(v[14], v[15])));
    m0 = fmaxf(m0, __shfl_xor_sync(0xffffffffu, m0, 1));
    m1 = fmaxf(m1, __shfl_xor_sync(0xffffffffu, m1, 1));
    m0 = fmaxf(m0, __shfl_xor_sync(0xffffffffu, m0, 2));
    m1 = fmaxf(m1, __shfl_xor_sync(0xffffffffu, m1, 2));
    const float sc = 0.0625f * 1.4426950408889634f;
    const float b0 = m0 * sc, b1 = m1 * sc;
    float s0 = 0.f, s1 = 0.f;
#pragma unroll
    for (int j = 0; j < 4; j++) {
        v[4 * j + 0] = ex2(fmaf(v[4 * j + 0], sc, -b0));
        v[4 * j + 1] = ex2(fmaf(v[4 * j + 1], sc, -b0));
        v[4 * j + 2] = ex2(fmaf(v[4 * j + 2], sc, -b1));
        v[4 * j + 3] = ex2(fmaf(v[4 * j + 3], sc, -b1));
        s0 += v[4 * j + 0] + v[4 * j + 1];
        s1 += v[4 * j + 2] + v[4 * j + 3];
    }
    s0 += __shfl_xor_sync(0xffffffffu, s0, 1);
    s1 += __shfl_xor_sync(0xffffffffu, s1, 1);
    s0 += __shfl_xor_sync(0xffffffffu, s0, 2);
    s1 += __shfl_xor_sync(0xffffffffu, s1, 2);
    const float r0 = __fdividef(1.f, s0), r1 = __fdividef(1.f, s1);
#pragma unroll
    for (int j = 0; j < 4; j++) {
        pa[2 * j + 0] = pack_bf16(v[4 * j + 0] * r0, v[4 * j + 1] * r0);
        pa[2 * j + 1] = pack_bf16(v[4 * j + 2] * r1, v[4 * j + 3] * r1);
    }
}

template <int H, int Q>
__device__ __forceinline__ void pv_issue(Ctx& c, float (&o)[32], const uint32_t (&pa)[8]) {
    if constexpr ((Q & 1) == 0) wait_full_w<idxV(H, 0, Q / 2)>(c);
    const uint32_t v0 = c.base16 + (slot_off_w<idxV(H, 0, Q / 2)>(c) >> 4);
    const uint32_t meta = c.warp >= 2 ? 0xEEEEEEEEu : 0x44444444u;
    wgmma_fence();
    wgmma_sp_rs_n64_tb1<((H == 0 && Q == 0) ? 0 : 2)>(o, pa[0], pa[1], pa[2], pa[3], mk_desc(v0, (Q & 1) * 8192, 8192), meta);
    wgmma_sp_rs_n64_tb1<1>(o, pa[4], pa[5], pa[6], pa[7], mk_desc(v0, (Q & 1) * 8192 + 4096, 8192), meta);
    wgmma_commit();
}
template <int N>
__device__ __forceinline__ void pack_regs(uint32_t* o, float (&a)[2 * N]) {
    fence_regs(a);
#pragma unroll
    for (int i = 0; i < N; i++) o[i] = pack_bf16_v(a[2 * i], a[2 * i + 1]);
}

template <int N, bool FIRST>
__device__ __forceinline__ void g2_tile(Ctx& c, float (&acc)[32], const uint32_t (&o)[64]) {
    constexpr int I = idxWo(N);
    wait_full<I>(c);
    wgmma_fence();
    constexpr uint32_t wo = TI<I>::slot * SLOT_BYTES;
#pragma unroll
    for (int kk = 0; kk < 8; kk++) {
        const int k = (TI<I>::c & 1) * 8 + kk;
        uint64_t d = mk_desc(c.base16, wo + kk * 2048, 8192);
        if (FIRST && kk == 0) wgmma_rs_n64_tb1<2>(acc, o[4 * k], o[4 * k + 1], o[4 * k + 2], o[4 * k + 3], d);
        else wgmma_rs_n64_tb1<1>(acc, o[4 * k], o[4 * k + 1], o[4 * k + 2], o[4 * k + 3], d);
    }
    wgmma_commit();
}
template <int C>
__device__ __forceinline__ uint32_t stash_addr(Ctx& c) {
    return c.sbase + TI<idxStg(C)>::slot * SLOT_BYTES + (c.wg * 4 + c.warp) * 2048;
}
template <int C>
__device__ __forceinline__ void g2_stash(Ctx& c, float (&acc)[32]) {
    fence_regs(acc);
    mbar_wait(c.sbase + EMPTY_OFF + idxStg(C) * 8, c.budget);
    const uint32_t a = stash_addr<C>(c) + c.lane * 16;
#pragma unroll
    for (int i = 0; i < 4; i++)
        asm volatile("st.shared.v4.b32 [%0], {%1, %2, %3, %4};" ::"r"(a + i * 512),
                     "r"(pack_bf16(acc[8 * i + 0], acc[8 * i + 1])), "r"(pack_bf16(acc[8 * i + 2], acc[8 * i + 3])),
                     "r"(pack_bf16(acc[8 * i + 4], acc[8 * i + 5])), "r"(pack_bf16(acc[8 * i + 6], acc[8 * i + 7])) : "memory");
}
struct OutCtx { const CUtensorMap* omap; int col0, rot, row0; };
template <int C, int R, int WAITN>
__device__ __forceinline__ void g2_stage(Ctx& c, float (&acc)[32]) {
    fence_regs(acc);
    const uint32_t buf = stash_addr<R>(c);
    uint32_t r[16];
    if constexpr (C < NSTG) {
        static_assert(C == R, "");
#pragma unroll
        for (int i = 0; i < 4; i++)
            asm volatile("ld.shared.v4.b32 {%0, %1, %2, %3}, [%4];" : "=r"(r[4 * i]), "=r"(r[4 * i + 1]), "=r"(r[4 * i + 2]), "=r"(r[4 * i + 3])
                         : "r"(buf + c.lane * 16 + i * 512) : "memory");
#pragma unroll
        for (int i = 0; i < 16; i++)
            asm("add.rn.bf16x2 %0, %1, %2;" : "=r"(r[i]) : "r"(r[i]), "r"(pack_bf16(acc[2 * i], acc[2 * i + 1])));
    } else {
#pragma unroll
        for (int i = 0; i < 16; i++) r[i] = pack_bf16(acc[2 * i], acc[2 * i + 1]);
    }
    if constexpr (WAITN >= 0) asm volatile("cp.async.bulk.wait_group.read %0;" ::"n"(WAITN) : "memory");
    __syncwarp();
    const int m = c.lane >> 3, row = (m & 1) * 8 + (c.lane & 7);
#pragma unroll
    for (int j = 0; j < 8; j += 2) {
        const int nt = j + (m >> 1);
        stmatrix_x4(buf + row * 128 + ((nt ^ (row & 7)) << 4), r[2 * j], r[2 * j + 1], r[2 * j + 2], r[2 * j + 3]);
    }
}
template <int C, int R>
__device__ __forceinline__ void g2_store(Ctx& c, const OutCtx& oc) {
    if constexpr (C == 0) mbar_wait(c.sbase + OUTRDY_OFF, c.budget);
    asm volatile("fence.proxy.async.shared::cta;" ::: "memory");
    __syncwarp();
    if (elect_one()) {
        int cc = C + oc.rot; if (cc >= NCHUNK) cc -= NCHUNK;
        tma_red_2d(oc.omap, stash_addr<R>(c), oc.col0 + cc * 64, oc.row0);
        asm volatile("cp.async.bulk.commit_group;" ::: "memory");
    }
}
template <int G>
__device__ __forceinline__ void g2_pre(Ctx& c, float (&acc)[32], float (&prev)[32], const uint32_t (&o)[64]) {
    g2_tile<2 * G, true>(c, acc, o);
    wgmma_wait<1>();
    release<idxWo(2 * G - 1)>(c);
    g2_stash<G - 1>(c, prev);
    g2_tile<2 * G + 1, false>(c, acc, o);
    wgmma_wait<1>();
    release<idxWo(2 * G)>(c);
}
template <int G, bool FIRST, int RC, int RR, int WAITN>
__device__ __forceinline__ void g2_pair(Ctx& c, float (&acc)[32], float (&prev)[32], const uint32_t (&o)[64], const OutCtx& oc) {
    g2_tile<2 * G, FIRST>(c, acc, o);
    wgmma_wait<1>();
    release<idxWo(2 * G - 1)>(c);
    if constexpr (RC >= 0) g2_stage<RC, RR, WAITN>(c, prev);
    g2_tile<2 * G + 1, false>(c, acc, o);
    if constexpr (RC >= 0) g2_store<RC, RR>(c, oc);
    wgmma_wait<1>();
    release<idxWo(2 * G)>(c);
}

constexpr int PF_N = 39;
constexpr int PF_N1 = 6;
__device__ __forceinline__ uint64_t pf_entry(const Maps& maps, int i, int p, int hp, int mt) {
    const uint32_t bstride = (p == 0 ? 8 : 16) * 16384;
    const uint32_t kv0 = mt * 4 * bstride + (p == 0 ? hp : 2 * hp) * 16384;
    const uint32_t kv1 = (mt * 4 + p * 2) * (16 * 16384) + (2 * hp + 1) * 16384;
    const uint32_t wq = mt * 8192 + hp * 1024;
    const uint32_t wo = (hp * 512 + mt * 32) * 896;
    const uint8_t* b;
    uint32_t o, sa = 4, sb = 2;
    if (i < 1) { b = maps.px[p]; o = (mt * 128 + hp * 16) * 896 + 640; sa = 7; sb = 1; }
    else if (i < 3) { b = maps.pwq[p]; o = wq + 512 + (288 + (i - 1) * 32) * 8192; sa = 512; }
    else if (i < 7) { b = maps.pwq[p]; o = wq + min((i - 3) * 128, 320) * 8192; sa = 512; }
    else if (i < 15) { b = maps.pk[p]; o = kv0 + ((i - 7) >> 1) * bstride + ((i - 7) & 1) * 8192; }
    else if (i < 19) { b = maps.pwo[p]; o = wo + min((i - 15) * 8192, 28672 - 8192); }
    else if (i < 27) { b = maps.pv[p]; o = kv0 + ((i - 19) >> 1) * bstride + ((i - 19) & 1) * 8192; }
    else if (i < 31) { b = maps.pk[1]; o = kv1 + ((i - 27) >> 1) * (16 * 16384) + ((i - 27) & 1) * 8192; }
    else if (i < 35) { b = maps.pv[1]; o = kv1 + ((i - 31) >> 1) * (16 * 16384) + ((i - 31) & 1) * 8192; }
    else { b = maps.pwo[p]; o = wo + 256 * 896 + min((i - 35) * 8192, 28672 - 8192); }
    return ((uint64_t)b + o) | ((uint64_t)sa << 48) | sb;
}

template <int D>
__device__ __forceinline__ void pf_run(uint32_t (&r)[5], uint64_t tab0, uint64_t tab1, int beg, int end, int lane, uint32_t zmask) {
#pragma unroll 1
    for (int i0 = beg; i0 < end; i0 += D) {
#pragma unroll
        for (int d = 0; d < D; d++) {
            const int i = i0 + d;
            if (i < end) {
                const uint64_t e = __shfl_sync(0xffffffffu, i < 32 ? tab0 : tab1, i);
                const uint32_t off = (((uint32_t)(e >> 48)) * (lane >> 1) + ((uint32_t)e & 7u) * (lane & 1)) * 128u;
                const uint64_t a = (e & 0xffffffffff80ull) + (off + (r[d] & zmask));
                asm volatile("ld.global.cg.L2::256B.u32 %0, [%1];" : "=r"(r[d]) : "l"(a) : "memory");
            }
        }
    }
}

template <int I>
__device__ __forceinline__ void produce(uint32_t sbase, const Maps& maps, int p, int hp, int mt, int rot, int& budget, uint32_t t_entry) {
    if constexpr (I < NREAL) {
        constexpr int kind = TI<I>::kind;
        if constexpr (I >= NEARLY) {
            if constexpr (I >= NSLOT) mbar_wait(sbase + EMPTY_OFF + I * 8, budget);
            else { while ((int)((uint32_t)clock() - t_entry) < STAG_T0 + (I - NEARLY) * STAG) {} }
            const uint32_t bar = sbase + FULL_OFF + I * 8;
            const uint32_t dst = sbase + TI<I>::slot * SLOT_BYTES;
            if constexpr (kind == T_X) {
                tma_2d(dst, &maps.x[p], bar, TI<I>::a * 64, mt * 128);
            } else if constexpr (kind == T_WQ) {
                tma_3d(dst, &maps.wq[p], bar, 0, TI<I>::b * 32, (hp * 2 + 1 - TI<I>::a) * 4);
            } else if constexpr (kind == T_K) {
                const int hkv = p == 0 ? hp : hp * 2 + TI<I>::a;
                tma_4d(dst, &maps.k[p], bar, 0, hkv * 32, mt * 4 + TI<I>::b * 2, TI<I>::c * 2);
            } else if constexpr (kind == T_V) {
                const int hkv = p == 0 ? hp : hp * 2 + TI<I>::a;
                tma_5d(dst, &maps.v[p], bar, 0, 0, mt * 4 + TI<I>::b * 2, hkv * 16, TI<I>::c * 2);
            } else if constexpr (kind == T_WO) {
                int cc = TI<I>::b + rot; if (cc >= NCHUNK) cc -= NCHUNK;
                tma_2d(dst, &maps.wo[p], bar, cc * 64, hp * 512 + TI<I>::c * 128);
            }
        }
        produce<I + 2>(sbase, maps, p, hp, mt, rot, budget, t_entry);
    }
}

__global__ void __launch_bounds__(384, 1)
fused_attn_kernel(const __grid_constant__ Maps maps, __nv_bfloat16* __restrict__ out) {
    extern __shared__ __align__(1024) uint8_t smem_raw[];
    const uint32_t sbase = (uint32_t)__cvta_generic_to_shared(smem_raw);
    if ((sbase & 0xFFFFFFu) != SMEM_START) return;
    const uint32_t t_entry = (uint32_t)clock();
    const int tid = threadIdx.x;
    const int wgi = __shfl_sync(0xffffffffu, tid >> 7, 0);
    const int warp = __shfl_sync(0xffffffffu, (tid >> 5) & 3, 0);
    const int lane = tid & 31;
    const int p = blockIdx.x >> 6, hp = (blockIdx.x >> 3) & 7, mt = (blockIdx.x + 3 * hp) & 7;
    const int rot = hp == 7 ? 0 : hp;

    uint64_t tab0 = 0, tab1 = 0;
    if (wgi == 2) {
        const bool el = elect_one();
        if (warp == 2) {
            tab0 = pf_entry(maps, lane, p, hp, mt);
            tab1 = pf_entry(maps, lane + 32, p, hp, mt);
        } else if (el) {
#pragma unroll 1
            for (int i = warp == 3 ? 2 : warp; i < NEARLY; i += 3) {
                const uint32_t bar = sbase + FULL_OFF + i * 8;
                mbar_init(bar, 1);
                mbar_expect_tx(bar, SLOT_BYTES);
                asm volatile("fence.proxy.async.shared::cta;" ::: "memory");
                const int i3 = i / 3, r3 = i - 3 * i3;
                if (r3 == 0) {
                    tma_2d(sbase + i * SLOT_BYTES, &maps.x[p], bar, i3 * 64, mt * 128);
                } else {
                    const int j = i3 * 2 + r3 - 1;
                    tma_3d(sbase + i * SLOT_BYTES, &maps.wq[p], bar, 0, j * 32, hp * 8 + 4);
                }
            }
        }
    } else {
        if (elect_one()) {
            const int w8 = wgi * 4 + warp;
#pragma unroll 1
            for (int i = NEARLY + w8; i < NT; i += 8) {
                mbar_init(sbase + FULL_OFF + i * 8, 1);
                mbar_init(sbase + EMPTY_OFF + i * 8, 8);
                mbar_expect_tx(sbase + FULL_OFF + i * 8, SLOT_BYTES);
            }
            if (w8 == 7) mbar_init(sbase + OUTRDY_OFF, 1);
            asm volatile("fence.proxy.async.shared::cta;" ::: "memory");
        }
    }
    __syncthreads();

    if (wgi == 2) {
        asm volatile("setmaxnreg.dec.sync.aligned.u32 24;");
        if (warp == 0) {
            if (elect_one()) {
                int budget = WAIT_BUDGET;
                produce<0>(sbase, maps, p, hp, mt, rot, budget, t_entry);
            }
        } else if (warp == 1) {
            if (elect_one()) {
                int budget = WAIT_BUDGET;
                produce<1>(sbase, maps, p, hp, mt, rot, budget, t_entry);
            }
        } else if (warp == 2) {
            const uint32_t zmask = maps.zero;
            uint32_t r[5];
#pragma unroll
            for (int i = 0; i < 5; i++) r[i] = 0;
            pf_run<3>(r, tab0, tab1, 0, PF_N1, lane, zmask);
            pf_run<5>(r, tab0, tab1, PF_N1, PF_N, lane, zmask);
            uint32_t acc = 0;
#pragma unroll
            for (int i = 0; i < 5; i++) acc |= r[i] & zmask;
            if (acc) g_zero_ctr[0] = acc;
        } else {
            if (lane == 0) {
                prefetch_map(&maps.k[p]);
                prefetch_map(&maps.v[p]);
                prefetch_map(&maps.wo[p]);
                prefetch_map(&maps.out);
            }
            uint8_t* base = reinterpret_cast<uint8_t*>(out) + (size_t)(mt * 128 + hp * 16) * 1792 + p * 896;
#pragma unroll 4
            for (int i = 0; i < 28; i++) {
                const int e = i * 32 + lane;
                const int r = e / 56, cidx = e - r * 56;
                *reinterpret_cast<uint4*>(base + r * 1792 + cidx * 16) = make_uint4(0, 0, 0, 0);
            }
            asm volatile("fence.proxy.async;" ::: "memory");
            __threadfence();
            __syncwarp();
            if (lane == 0) {
                unsigned int* ctr = &g_zero_ctr[p * 8 + mt];
                const unsigned int old = atomicAdd(ctr, 1u);
                const unsigned int target = (old & ~7u) + 8u;
                int it = 0;
                while (true) {
                    unsigned int cur;
                    asm volatile("ld.acquire.gpu.global.u32 %0, [%1];" : "=r"(cur) : "l"(ctr) : "memory");
                    if ((int)(cur - target) >= 0) break;
                    if (++it > (1 << 20)) break;
                    __nanosleep(256);
                }
                asm volatile("fence.proxy.async;" ::: "memory");
                mbar_arrive(sbase + OUTRDY_OFF, 1u);
            }
        }
    } else {
        asm volatile("setmaxnreg.inc.sync.aligned.u32 240;");
        Ctx c;
        c.budget = WAIT_BUDGET; c.sbase = sbase; c.lane = lane; c.wg = wgi; c.warp = warp;
        OutCtx oc;
        oc.omap = &maps.out; oc.col0 = p * 448; oc.rot = rot; oc.row0 = mt * 128 + wgi * 64 + warp * 16;

        uint32_t pa[8];
        uint32_t o0[64], o1[64];
        float a0[32], a1[32];
        {
            uint32_t q1[64];
            {
                uint32_t q0[64];
                {
                    float acc[128];
                    g1_range<0, 0>(c, acc);
#pragma unroll
                    for (int i = 0; i < 64; i++) q1[i] = pack_bf16(acc[2 * i], acc[2 * i + 1]);
                    g1_range<1, 0>(c, acc);
#pragma unroll
                    for (int i = 63; i >= 0; i--) q0[i] = pack_bf16_v(acc[2 * i], acc[2 * i + 1]);
                }
                s_issue<0>(c, a0, q0);
                wgmma_wait<0>();
            }
            fence_regs(a0);
            release_w<idxK(0, 0, 0)>(c);
            release_w<idxK(0, 0, 1)>(c);
            softmax(c, a0, pa);
            pv_issue<0, 0>(c, a1, pa);
            pv_issue<0, 1>(c, a0, pa);
            wgmma_wait<1>();
            pack_regs<16>(o0, a1);
            pv_issue<0, 2>(c, a1, pa);
            wgmma_wait<1>();
            release_w<idxV(0, 0, 0)>(c);
            pack_regs<16>(o0 + 16, a0);
            pv_issue<0, 3>(c, a0, pa);
            wgmma_wait<1>();
            pack_regs<16>(o0 + 32, a1);
            g2_tile<0, true>(c, a1, o0);
            wgmma_wait<1>();
            release_w<idxV(0, 0, 1)>(c);
            pack_regs<16>(o0 + 48, a0);
            g2_tile<1, false>(c, a1, o0);
            wgmma_wait<1>();
            release<idxWo(0)>(c);
            g2_pre<1>(c, a0, a1, o0);
            g2_pre<2>(c, a1, a0, o0);
            s_issue<1>(c, a0, q1);
            wgmma_wait<1>();
            release<idxWo(5)>(c);
            g2_stash<2>(c, a1);
            g2_tile<6, true>(c, a1, o0);
            wgmma_wait<1>();
        }
        fence_regs(a0);
        release_w<idxK(1, 0, 0)>(c);
        release_w<idxK(1, 0, 1)>(c);
        g2_tile<7, false>(c, a1, o0);
        softmax(c, a0, pa);
        pv_issue<1, 0>(c, a0, pa);
        wgmma_wait<1>();
        release<idxWo(6)>(c);
        release<idxWo(7)>(c);
        g2_stash<3>(c, a1);
        pv_issue<1, 1>(c, a1, pa);
        wgmma_wait<1>();
        pack_regs<16>(o1, a0);
        pv_issue<1, 2>(c, a0, pa);
        wgmma_wait<1>();
        release_w<idxV(1, 0, 0)>(c);
        pack_regs<16>(o1 + 16, a1);
        pv_issue<1, 3>(c, a1, pa);
        wgmma_wait<1>();
        pack_regs<16>(o1 + 32, a0);
        g2_tile<8, true>(c, a0, o0);
        wgmma_wait<1>();
        release_w<idxV(1, 0, 1)>(c);
        pack_regs<16>(o1 + 48, a1);
        g2_tile<9, false>(c, a0, o0);
        wgmma_wait<1>();
        release<idxWo(8)>(c);
        g2_pair<5, true, -1, 0, -1>(c, a1, a0, o1, oc);
        g2_pair<6, false, 0, 0, -1>(c, a0, a1, o1, oc);
        g2_pair<7, true, 4, 0, 0>(c, a1, a0, o1, oc);
        g2_pair<8, true, 1, 1, -1>(c, a0, a1, o0, oc);
        g2_pair<9, false, -1, 0, -1>(c, a0, a1, o1, oc);
        g2_pair<10, true, 5, 0, 1>(c, a1, a0, o1, oc);
        g2_pair<11, true, 2, 2, -1>(c, a0, a1, o1, oc);
        g2_pair<12, true, 3, 3, -1>(c, a1, a0, o0, oc);
        g2_pair<13, false, -1, 0, -1>(c, a1, a0, o1, oc);
        wgmma_wait<0>();
        g2_stage<6, 1, 3>(c, a1);
        g2_store<6, 1>(c, oc);
        asm volatile("cp.async.bulk.wait_group.read 0;" ::: "memory");
    }
}

typedef CUresult (*EncodeFn)(CUtensorMap*, CUtensorMapDataType, cuuint32_t, void*, const cuuint64_t*, const cuuint64_t*,
                             const cuuint32_t*, const cuuint32_t*, CUtensorMapInterleave, CUtensorMapSwizzle,
                             CUtensorMapL2promotion, CUtensorMapFloatOOBfill);

void encode(EncodeFn fn, CUtensorMap* m, const void* ptr, int rank, const cuuint64_t* dims, const cuuint64_t* strides,
            const cuuint32_t* box) {
    cuuint32_t es[5] = {1, 1, 1, 1, 1};
    fn(m, CU_TENSOR_MAP_DATA_TYPE_BFLOAT16, rank, const_cast<void*>(ptr), dims, strides, box, es,
       CU_TENSOR_MAP_INTERLEAVE_NONE, CU_TENSOR_MAP_SWIZZLE_128B, CU_TENSOR_MAP_L2_PROMOTION_L2_128B,
       CU_TENSOR_MAP_FLOAT_OOB_FILL_NONE);
}

}

extern "C" void kernel_launch(void* const* d_in, const int* in_sizes, int n_in, void* d_out, int out_size) {
    static EncodeFn fn = nullptr;
    if (!fn) {
        void* f = nullptr;
        cudaDriverEntryPointQueryResult q;
        cudaGetDriverEntryPoint("cuTensorMapEncodeTiled", &f, cudaEnableDefault, &q);
        fn = (EncodeFn)f;
        cudaFuncSetAttribute(fused_attn_kernel, cudaFuncAttributeMaxDynamicSharedMemorySize, SMEM_BYTES);
    }
    Maps maps;
    maps.zero = 0;
    for (int p = 0; p < 2; p++) {
        const int H = p == 0 ? 8 : 16;
        void* x = d_in[p * 5 + 0];
        void* kc = d_in[p * 5 + 1];
        void* vc = d_in[p * 5 + 2];
        void* wq = d_in[p * 5 + 3];
        void* wo = d_in[p * 5 + 4];
        maps.px[p] = (const uint8_t*)x; maps.pk[p] = (const uint8_t*)kc; maps.pv[p] = (const uint8_t*)vc;
        maps.pwq[p] = (const uint8_t*)wq; maps.pwo[p] = (const uint8_t*)wo;
        {
            cuuint64_t d[2] = {448, 1024}, s[1] = {896};
            cuuint32_t b[2] = {64, 128};
            encode(fn, &maps.x[p], x, 2, d, s, b);
        }
        {
            cuuint64_t d[3] = {64, 448, 64}, s[2] = {8192, 128};
            cuuint32_t b[3] = {64, 32, 4};
            encode(fn, &maps.wq[p], wq, 3, d, s, b);
        }
        {
            cuuint64_t d[4] = {64, (cuuint64_t)H * 32, 32, 4}, s[3] = {512, (cuuint64_t)H * 16384, 128};
            cuuint32_t b[4] = {64, 32, 2, 2};
            encode(fn, &maps.k[p], kc, 4, d, s, b);
        }
        {
            cuuint64_t d[5] = {64, 2, 32, (cuuint64_t)H * 16, 4}, s[4] = {512, (cuuint64_t)H * 16384, 1024, 128};
            cuuint32_t b[5] = {64, 2, 2, 16, 2};
            encode(fn, &maps.v[p], vc, 5, d, s, b);
        }
        {
            cuuint64_t d[2] = {448, 4096}, s[1] = {896};
            cuuint32_t b[2] = {64, 128};
            encode(fn, &maps.wo[p], wo, 2, d, s, b);
        }
    }
    {
        cuuint64_t d[2] = {896, 1024}, s[1] = {1792};
        cuuint32_t b[2] = {64, 16};
        encode(fn, &maps.out, d_out, 2, d, s, b);
    }
    fused_attn_kernel<<<128, 384, SMEM_BYTES>>>(maps, (__nv_bfloat16*)d_out);
}
```
